```python
import torch

def _softmax(x, axis=-1):
    return torch.softmax(x, dim=axis)
def _gelu(x):
    return torch.nn.functional.gelu(x, approximate="tanh")
def _silu(x):
    return torch.nn.functional.silu(x)
def _sigmoid(x):
    return torch.sigmoid(x)
def _layernorm(x, axis=-1, eps=1e-5):
    m = x.mean(dim=axis, keepdim=True)
    v = x.var(dim=axis, keepdim=True, unbiased=False)
    return (x - m) / torch.sqrt(v + eps)
def _scatter_add(tgt, idx, src, axis=0):
    return tgt.clone().index_add_(axis, idx, src)
def _segment_sum(src, seg, n):
    out = torch.zeros((n,) + src.shape[1:], dtype=src.dtype)
    return out.index_add_(0, seg, src)
def _pad(x, pw):
    flat = tuple(v for pair in reversed(pw) for v in pair)
    return torch.nn.functional.pad(x, flat)

kernel_name = 'standalone__mha_block_cached__near_ridge'

def setup_inputs():

    _w = (lambda a: (lambda t: t.to(torch.bfloat16) if t.is_floating_point() else t)(torch.as_tensor(a)))
    B, Sq, D = 8, 224, 512
    H, Sk, Dh = 32, 1024, 128
    return {
        "x": _w((lambda *s: torch.randn(*s, dtype=torch.bfloat16) * 0.8)(B, Sq, D)),
        "k_cache": _w((lambda *s: torch.randn(*s, dtype=torch.bfloat16) * 0.8)(B, H, Sk, Dh)),
        "v_cache": _w((lambda *s: torch.randn(*s, dtype=torch.bfloat16) * 0.05)(B, H, Sk, Dh)),
        "wq": _w((lambda *s: torch.randn(*s, dtype=torch.bfloat16) * 0.8)(D, H * Dh) * (D ** -0.5)),
        "wo": _w((lambda *s: torch.randn(*s, dtype=torch.bfloat16) * 0.05)(H * Dh, D) * ((H * Dh) ** -0.5)),
    }

def reference(x, k_cache, v_cache, wq, wo):
    B, Sq, D = x.shape
    H, Dh = 32, 128
    q = (lambda x, *d: x.permute(*d))((x @ wq).reshape(B, Sq, H, Dh), 0, 2, 1, 3)
    scores = torch.einsum("bhqd,bhkd->bhqk", q, k_cache) * (Dh ** -0.5)
    p = _softmax(scores, axis=-1)
    o = torch.einsum("bhqk,bhkd->bhqd", p, v_cache)
    return (lambda x, *d: x.permute(*d))(o, 0, 2, 1, 3).reshape(B, Sq, H * Dh) @ wo
```

```cpp
#include <cuda_runtime.h>
#include <cuda_bf16.h>
#include <cuda.h>
#include <stdint.h>

namespace {

constexpr int NB = 8, SQ = 224, DM = 512, NH = 32, SK = 1024, DH = 128;
constexpr int ROWS = NB * SQ;
constexpr int HD = NH * DH;

__device__ __align__(128) __nv_bfloat16 g_O[ROWS * HD];
__device__ __align__(128) uint8_t g_Q2[128 * 16384];
__device__ uint4 g_part[128 * 3 * 4 * 256];
__device__ __align__(128) uint32_t g_sync[128 * 32];

__device__ __forceinline__ uint32_t smem_u32(const void* p) { return (uint32_t)__cvta_generic_to_shared(p); }
__device__ __forceinline__ void mbar_init(uint32_t bar, int cnt) {
  asm volatile("mbarrier.init.shared::cta.b64 [%0], %1;" :: "r"(bar), "r"(cnt) : "memory");
}
__device__ __forceinline__ void mbar_expect_tx(uint32_t bar, uint32_t bytes) {
  asm volatile("mbarrier.arrive.expect_tx.shared::cta.b64 _, [%0], %1;" :: "r"(bar), "r"(bytes) : "memory");
}
__device__ __forceinline__ void mbar_arrive(uint32_t bar) {
  asm volatile("mbarrier.arrive.shared::cta.b64 _, [%0];" :: "r"(bar) : "memory");
}
__device__ __forceinline__ void mbar_wait(uint32_t bar, uint32_t parity) {
  asm volatile(
    "{\n.reg .pred p;\n.reg .u32 n;\nmov.u32 n, 0;\n"
    "WAIT_%=:\n"
    "mbarrier.try_wait.parity.shared::cta.b64 p, [%0], %1;\n"
    "@p bra DONE_%=;\n"
    "add.u32 n, n, 1;\n"
    "setp.lt.u32 p, n, 4000000;\n"
    "@p bra WAIT_%=;\n"
    "trap;\n"
    "DONE_%=:\n}\n" :: "r"(bar), "r"(parity) : "memory");
}
__device__ __forceinline__ void tma_load_2d(uint32_t dst, const CUtensorMap* tm, uint32_t bar, int c0, int c1) {
  asm volatile("cp.async.bulk.tensor.2d.shared::cluster.global.mbarrier::complete_tx::bytes [%0], [%1, {%3, %4}], [%2];"
    :: "r"(dst), "l"(tm), "r"(bar), "r"(c0), "r"(c1) : "memory");
}
__device__ __forceinline__ void tma_load_3d(uint32_t dst, const CUtensorMap* tm, uint32_t bar, int c0, int c1, int c2) {
  asm volatile("cp.async.bulk.tensor.3d.shared::cluster.global.mbarrier::complete_tx::bytes [%0], [%1, {%3, %4, %5}], [%2];"
    :: "r"(dst), "l"(tm), "r"(bar), "r"(c0), "r"(c1), "r"(c2) : "memory");
}
__device__ __forceinline__ void tma_load_3d_stream(uint32_t dst, const CUtensorMap* tm, uint32_t bar, int c0, int c1, int c2) {
  asm volatile("{\n.reg .b64 pol;\ncreatepolicy.fractional.L2::evict_first.b64 pol, 1.0;\n"
    "cp.async.bulk.tensor.3d.shared::cluster.global.mbarrier::complete_tx::bytes.L2::cache_hint [%0], [%1, {%3, %4, %5}], [%2], pol;\n}\n"
    :: "r"(dst), "l"(tm), "r"(bar), "r"(c0), "r"(c1), "r"(c2) : "memory");
}
__device__ __forceinline__ void refill_stream(uint32_t full_bar, uint32_t parity, uint32_t dst, const CUtensorMap* tm, int row) {
  asm volatile(
    "{\n.reg .pred p;\n.reg .u32 n;\n.reg .b64 pol;\nmov.u32 n, 0;\n"
    "mov.b64 pol, 0x12F0000000000000;\n"
    "WAIT_%=:\n"
    "mbarrier.try_wait.parity.shared::cta.b64 p, [%0+32], %1;\n"
    "@p bra DONE_%=;\n"
    "add.u32 n, n, 1;\n"
    "setp.lt.u32 p, n, 4000000;\n"
    "@p bra WAIT_%=;\n"
    "trap;\n"
    "DONE_%=:\n"
    "elect.sync _|p, 0xffffffff;\n"
    "@p mbarrier.arrive.expect_tx.shared::cta.b64 _, [%0], 32768;\n"
    "@p cp.async.bulk.tensor.3d.shared::cluster.global.mbarrier::complete_tx::bytes.L2::cache_hint [%2], [%3, {0, %4, 0}], [%0], pol;\n"
    "}\n" :: "r"(full_bar), "r"(parity), "r"(dst), "l"(tm), "r"(row) : "memory");
}
__device__ __forceinline__ void tma_store_2d(const CUtensorMap* tm, uint32_t src, int c0, int c1) {
  asm volatile("cp.async.bulk.tensor.2d.global.shared::cta.bulk_group [%0, {%2, %3}], [%1];"
    :: "l"(tm), "r"(src), "r"(c0), "r"(c1) : "memory");
}
__device__ __forceinline__ void bulk_load(uint32_t dst, const void* src, uint32_t bytes, uint32_t bar) {
  asm volatile("cp.async.bulk.shared::cluster.global.mbarrier::complete_tx::bytes [%0], [%1], %2, [%3];"
    :: "r"(dst), "l"(src), "r"(bytes), "r"(bar) : "memory");
}
__device__ __forceinline__ void bulk_store(void* dst, uint32_t src, uint32_t bytes) {
  asm volatile("cp.async.bulk.global.shared::cta.bulk_group [%0], [%1], %2;" :: "l"(dst), "r"(src), "r"(bytes) : "memory");
}
__device__ __forceinline__ void l2_prefetch(const void* src, uint32_t bytes) {
  asm volatile("cp.async.bulk.prefetch.L2.global [%0], %1;" :: "l"(src), "r"(bytes) : "memory");
}
__device__ __forceinline__ void bulk_commit() { asm volatile("cp.async.bulk.commit_group;" ::: "memory"); }
__device__ __forceinline__ void bulk_wait_read0() { asm volatile("cp.async.bulk.wait_group.read 0;" ::: "memory"); }
__device__ __forceinline__ void bulk_wait0() { asm volatile("cp.async.bulk.wait_group 0;" ::: "memory"); }
__device__ __forceinline__ void fence_async_smem() { asm volatile("fence.proxy.async.shared::cta;" ::: "memory"); }
__device__ __forceinline__ void bar_sync(int id, int n) { asm volatile("bar.sync %0, %1;" :: "r"(id), "r"(n) : "memory"); }
__device__ __forceinline__ void bar_arrive(int id, int n) { asm volatile("bar.arrive %0, %1;" :: "r"(id), "r"(n) : "memory"); }
__device__ __forceinline__ void wg_fence() { asm volatile("wgmma.fence.sync.aligned;" ::: "memory"); }
__device__ __forceinline__ void wg_commit() { asm volatile("wgmma.commit_group.sync.aligned;" ::: "memory"); }
template <int N> __device__ __forceinline__ void wg_wait() { asm volatile("wgmma.wait_group.sync.aligned %0;" :: "n"(N) : "memory"); }
template <int N> __device__ __forceinline__ void reg_fence(float (&d)[N]) {
#pragma unroll
  for (int i = 0; i < N; i++) asm volatile("" : "+f"(d[i]) :: "memory");
}
template <int N> __device__ __forceinline__ void reg_fence(uint32_t (&d)[N]) {
#pragma unroll
  for (int i = 0; i < N; i++) asm volatile("" : "+r"(d[i]) :: "memory");
}
#define SCHED_FENCE() asm volatile("pmevent 0;" ::: "memory")
__device__ __forceinline__ uint32_t pack_bf16(float lo, float hi) {
  uint32_t r; asm("cvt.rn.bf16x2.f32 %0, %1, %2;" : "=r"(r) : "f"(hi), "f"(lo)); return r;
}
__device__ __forceinline__ float bf_lo(uint32_t v) { return __uint_as_float(v << 16); }
__device__ __forceinline__ float bf_hi(uint32_t v) { return __uint_as_float(v & 0xffff0000u); }
__device__ __forceinline__ float ex2(float x) { float y; asm("ex2.approx.ftz.f32 %0, %1;" : "=f"(y) : "f"(x)); return y; }
__device__ __forceinline__ void stmatrix_x4(uint32_t addr, uint32_t r0, uint32_t r1, uint32_t r2, uint32_t r3) {
  asm volatile("stmatrix.sync.aligned.m8n8.x4.shared.b16 [%0], {%1, %2, %3, %4};" :: "r"(addr), "r"(r0), "r"(r1), "r"(r2), "r"(r3) : "memory");
}
__device__ __forceinline__ void stmatrix_x4_t(uint32_t addr, uint32_t r0, uint32_t r1, uint32_t r2, uint32_t r3) {
  asm volatile("stmatrix.sync.aligned.m8n8.x4.trans.shared.b16 [%0], {%1, %2, %3, %4};" :: "r"(addr), "r"(r0), "r"(r1), "r"(r2), "r"(r3) : "memory");
}
__device__ __forceinline__ void stmatrix_x2_t(uint32_t addr, uint32_t r0, uint32_t r1) {
  asm volatile("stmatrix.sync.aligned.m8n8.x2.trans.shared.b16 [%0], {%1, %2};" :: "r"(addr), "r"(r0), "r"(r1) : "memory");
}
__device__ __forceinline__ uint32_t tid_now() { uint32_t t; asm volatile("mov.u32 %0, %%tid.x;" : "=r"(t)); return t; }
__device__ __forceinline__ uint32_t uni(uint32_t v) { return __shfl_sync(0xffffffffu, v, 0); }
__device__ __forceinline__ bool elect_one() {
  uint32_t p;
  asm volatile("{\n.reg .pred p;\nelect.sync _|p, 0xffffffff;\nselp.u32 %0, 1, 0, p;\n}\n" : "=r"(p));
  return p != 0;
}
__device__ __forceinline__ uint32_t ld_relaxed(const uint32_t* p) {
  uint32_t v; asm volatile("ld.relaxed.gpu.global.u32 %0, [%1];" : "=r"(v) : "l"(p) : "memory"); return v;
}
__device__ __forceinline__ void red_relaxed(uint32_t* p) {
  asm volatile("red.relaxed.gpu.global.add.u32 [%0], 1;" :: "l"(p) : "memory");
}
__device__ __forceinline__ void flag_wait(const uint32_t* p, uint32_t target) {
  for (uint32_t n = 0; (int)(ld_relaxed(p) - target) < 0; n++) { if (n > 20000000u) __trap(); }
}
__device__ __forceinline__ void st_b128(uint4* p, uint32_t a, uint32_t b, uint32_t c, uint32_t d) {
  asm volatile("{\n.reg .b128 t;\n.reg .b64 lo, hi;\nmov.b64 lo, {%1, %2};\nmov.b64 hi, {%3, %4};\nmov.b128 t, {lo, hi};\n"
               "st.relaxed.gpu.global.b128 [%0], t;\n}\n" :: "l"(p), "r"(a), "r"(b), "r"(c), "r"(d) : "memory");
}
__device__ __forceinline__ uint4 ld_b128(const uint4* p) {
  uint4 v;
  asm volatile("{\n.reg .b128 t;\n.reg .b64 lo, hi;\nld.relaxed.gpu.global.b128 t, [%4];\nmov.b128 {lo, hi}, t;\n"
               "mov.b64 {%0, %1}, lo;\nmov.b64 {%2, %3}, hi;\n}\n" : "=r"(v.x), "=r"(v.y), "=r"(v.z), "=r"(v.w) : "l"(p) : "memory");
  return v;
}
__device__ __forceinline__ uint32_t lds32(uint32_t a) { uint32_t v; asm volatile("ld.shared.u32 %0, [%1];" : "=r"(v) : "r"(a) : "memory"); return v; }
__device__ __forceinline__ void sts32(uint32_t a, uint32_t v) { asm volatile("st.shared.u32 [%0], %1;" :: "r"(a), "r"(v) : "memory"); }

__device__ __forceinline__ void gemm_qk_keep(float (&d)[64], uint32_t da, uint32_t db) {
  asm volatile(
    "{\n"
    ".reg .pred p, q, g;\n"
    ".reg .b64 da, db;\n"
    ".reg .b32 mt;\n"
    "setp.ne.b32 p, 0, 0;\n"
    "setp.eq.b32 q, 0, 0;\n"
    "mov.b64 da, {%64, 0x40000040};\n"
    "mov.b64 db, {%65, 0x40000040};\n"
    "wgmma.mma_async.sync.aligned.m64n128k16.f32.bf16.bf16 {%0, %1, %2, %3, %4, %5, %6, %7, %8, %9, %10, %11, %12, %13, %14, %15, %16, %17, %18, %19, %20, %21, %22, %23, %24, %25, %26, %27, %28, %29, %30, %31, %32, %33, %34, %35, %36, %37, %38, %39, %40, %41, %42, %43, %44, %45, %46, %47, %48, %49, %50, %51, %52, %53, %54, %55, %56, %57, %58, %59, %60, %61, %62, %63}, da, db, p, 1, 1, 0, 0;\n"
    "add.s64 da, da, 2;\n"
    "add.s64 db, db, 2;\n"
    "wgmma.mma_async.sync.aligned.m64n128k16.f32.bf16.bf16 {%0, %1, %2, %3, %4, %5, %6, %7, %8, %9, %10, %11, %12, %13, %14, %15, %16, %17, %18, %19, %20, %21, %22, %23, %24, %25, %26, %27, %28, %29, %30, %31, %32, %33, %34, %35, %36, %37, %38, %39, %40, %41, %42, %43, %44, %45, %46, %47, %48, %49, %50, %51, %52, %53, %54, %55, %56, %57, %58, %59, %60, %61, %62, %63}, da, db, q, 1, 1, 0, 0;\n"
    "add.s64 da, da, 2;\n"
    "add.s64 db, db, 2;\n"
    "wgmma.mma_async.sync.aligned.m64n128k16.f32.bf16.bf16 {%0, %1, %2, %3, %4, %5, %6, %7, %8, %9, %10, %11, %12, %13, %14, %15, %16, %17, %18, %19, %20, %21, %22, %23, %24, %25, %26, %27, %28, %29, %30, %31, %32, %33, %34, %35, %36, %37, %38, %39, %40, %41, %42, %43, %44, %45, %46, %47, %48, %49, %50, %51, %52, %53, %54, %55, %56, %57, %58, %59, %60, %61, %62, %63}, da, db, q, 1, 1, 0, 0;\n"
    "add.s64 da, da, 2;\n"
    "add.s64 db, db, 2;\n"
    "wgmma.mma_async.sync.aligned.m64n128k16.f32.bf16.bf16 {%0, %1, %2, %3, %4, %5, %6, %7, %8, %9, %10, %11, %12, %13, %14, %15, %16, %17, %18, %19, %20, %21, %22, %23, %24, %25, %26, %27, %28, %29, %30, %31, %32, %33, %34, %35, %36, %37, %38, %39, %40, %41, %42, %43, %44, %45, %46, %47, %48, %49, %50, %51, %52, %53, %54, %55, %56, %57, %58, %59, %60, %61, %62, %63}, da, db, q, 1, 1, 0, 0;\n"
    "add.s64 da, da, 506;\n"
    "add.s64 db, db, 1018;\n"
    "wgmma.mma_async.sync.aligned.m64n128k16.f32.bf16.bf16 {%0, %1, %2, %3, %4, %5, %6, %7, %8, %9, %10, %11, %12, %13, %14, %15, %16, %17, %18, %19, %20, %21, %22, %23, %24, %25, %26, %27, %28, %29, %30, %31, %32, %33, %34, %35, %36, %37, %38, %39, %40, %41, %42, %43, %44, %45, %46, %47, %48, %49, %50, %51, %52, %53, %54, %55, %56, %57, %58, %59, %60, %61, %62, %63}, da, db, q, 1, 1, 0, 0;\n"
    "add.s64 da, da, 2;\n"
    "add.s64 db, db, 2;\n"
    "wgmma.mma_async.sync.aligned.m64n128k16.f32.bf16.bf16 {%0, %1, %2, %3, %4, %5, %6, %7, %8, %9, %10, %11, %12, %13, %14, %15, %16, %17, %18, %19, %20, %21, %22, %23, %24, %25, %26, %27, %28, %29, %30, %31, %32, %33, %34, %35, %36, %37, %38, %39, %40, %41, %42, %43, %44, %45, %46, %47, %48, %49, %50, %51, %52, %53, %54, %55, %56, %57, %58, %59, %60, %61, %62, %63}, da, db, q, 1, 1, 0, 0;\n"
    "add.s64 da, da, 2;\n"
    "add.s64 db, db, 2;\n"
    "wgmma.mma_async.sync.aligned.m64n128k16.f32.bf16.bf16 {%0, %1, %2, %3, %4, %5, %6, %7, %8, %9, %10, %11, %12, %13, %14, %15, %16, %17, %18, %19, %20, %21, %22, %23, %24, %25, %26, %27, %28, %29, %30, %31, %32, %33, %34, %35, %36, %37, %38, %39, %40, %41, %42, %43, %44, %45, %46, %47, %48, %49, %50, %51, %52, %53, %54, %55, %56, %57, %58, %59, %60, %61, %62, %63}, da, db, q, 1, 1, 0, 0;\n"
    "add.s64 da, da, 2;\n"
    "add.s64 db, db, 2;\n"
    "wgmma.mma_async.sync.aligned.m64n128k16.f32.bf16.bf16 {%0, %1, %2, %3, %4, %5, %6, %7, %8, %9, %10, %11, %12, %13, %14, %15, %16, %17, %18, %19, %20, %21, %22, %23, %24, %25, %26, %27, %28, %29, %30, %31, %32, %33, %34, %35, %36, %37, %38, %39, %40, %41, %42, %43, %44, %45, %46, %47, %48, %49, %50, %51, %52, %53, %54, %55, %56, %57, %58, %59, %60, %61, %62, %63}, da, db, q, 1, 1, 0, 0;\n"
    "}\n"
    : "+f"(d[0]), "+f"(d[1]), "+f"(d[2]), "+f"(d[3]), "+f"(d[4]), "+f"(d[5]), "+f"(d[6]), "+f"(d[7]),
      "+f"(d[8]), "+f"(d[9]), "+f"(d[10]), "+f"(d[11]), "+f"(d[12]), "+f"(d[13]), "+f"(d[14]), "+f"(d[15]),
      "+f"(d[16]), "+f"(d[17]), "+f"(d[18]), "+f"(d[19]), "+f"(d[20]), "+f"(d[21]), "+f"(d[22]), "+f"(d[23]),
      "+f"(d[24]), "+f"(d[25]), "+f"(d[26]), "+f"(d[27]), "+f"(d[28]), "+f"(d[29]), "+f"(d[30]), "+f"(d[31]),
      "+f"(d[32]), "+f"(d[33]), "+f"(d[34]), "+f"(d[35]), "+f"(d[36]), "+f"(d[37]), "+f"(d[38]), "+f"(d[39]),
      "+f"(d[40]), "+f"(d[41]), "+f"(d[42]), "+f"(d[43]), "+f"(d[44]), "+f"(d[45]), "+f"(d[46]), "+f"(d[47]),
      "+f"(d[48]), "+f"(d[49]), "+f"(d[50]), "+f"(d[51]), "+f"(d[52]), "+f"(d[53]), "+f"(d[54]), "+f"(d[55]),
      "+f"(d[56]), "+f"(d[57]), "+f"(d[58]), "+f"(d[59]), "+f"(d[60]), "+f"(d[61]), "+f"(d[62]), "+f"(d[63])
    : "r"(da), "r"(db));
}
__device__ __forceinline__ void gemm_qk_fresh(float (&d)[64], uint32_t da, uint32_t db) {
  asm volatile(
    "{\n"
    ".reg .pred p, q, g;\n"
    ".reg .b64 da, db;\n"
    ".reg .b32 mt;\n"
    "setp.ne.b32 p, 0, 0;\n"
    "setp.eq.b32 q, 0, 0;\n"
    "mov.b64 da, {%64, 0x40000040};\n"
    "mov.b64 db, {%65, 0x40000040};\n"
    "wgmma.mma_async.sync.aligned.m64n128k16.f32.bf16.bf16 {%0, %1, %2, %3, %4, %5, %6, %7, %8, %9, %10, %11, %12, %13, %14, %15, %16, %17, %18, %19, %20, %21, %22, %23, %24, %25, %26, %27, %28, %29, %30, %31, %32, %33, %34, %35, %36, %37, %38, %39, %40, %41, %42, %43, %44, %45, %46, %47, %48, %49, %50, %51, %52, %53, %54, %55, %56, %57, %58, %59, %60, %61, %62, %63}, da, db, p, 1, 1, 0, 0;\n"
    "add.s64 da, da, 2;\n"
    "add.s64 db, db, 2;\n"
    "wgmma.mma_async.sync.aligned.m64n128k16.f32.bf16.bf16 {%0, %1, %2, %3, %4, %5, %6, %7, %8, %9, %10, %11, %12, %13, %14, %15, %16, %17, %18, %19, %20, %21, %22, %23, %24, %25, %26, %27, %28, %29, %30, %31, %32, %33, %34, %35, %36, %37, %38, %39, %40, %41, %42, %43, %44, %45, %46, %47, %48, %49, %50, %51, %52, %53, %54, %55, %56, %57, %58, %59, %60, %61, %62, %63}, da, db, q, 1, 1, 0, 0;\n"
    "add.s64 da, da, 2;\n"
    "add.s64 db, db, 2;\n"
    "wgmma.mma_async.sync.aligned.m64n128k16.f32.bf16.bf16 {%0, %1, %2, %3, %4, %5, %6, %7, %8, %9, %10, %11, %12, %13, %14, %15, %16, %17, %18, %19, %20, %21, %22, %23, %24, %25, %26, %27, %28, %29, %30, %31, %32, %33, %34, %35, %36, %37, %38, %39, %40, %41, %42, %43, %44, %45, %46, %47, %48, %49, %50, %51, %52, %53, %54, %55, %56, %57, %58, %59, %60, %61, %62, %63}, da, db, q, 1, 1, 0, 0;\n"
    "add.s64 da, da, 2;\n"
    "add.s64 db, db, 2;\n"
    "wgmma.mma_async.sync.aligned.m64n128k16.f32.bf16.bf16 {%0, %1, %2, %3, %4, %5, %6, %7, %8, %9, %10, %11, %12, %13, %14, %15, %16, %17, %18, %19, %20, %21, %22, %23, %24, %25, %26, %27, %28, %29, %30, %31, %32, %33, %34, %35, %36, %37, %38, %39, %40, %41, %42, %43, %44, %45, %46, %47, %48, %49, %50, %51, %52, %53, %54, %55, %56, %57, %58, %59, %60, %61, %62, %63}, da, db, q, 1, 1, 0, 0;\n"
    "add.s64 da, da, 506;\n"
    "add.s64 db, db, 1018;\n"
    "wgmma.mma_async.sync.aligned.m64n128k16.f32.bf16.bf16 {%0, %1, %2, %3, %4, %5, %6, %7, %8, %9, %10, %11, %12, %13, %14, %15, %16, %17, %18, %19, %20, %21, %22, %23, %24, %25, %26, %27, %28, %29, %30, %31, %32, %33, %34, %35, %36, %37, %38, %39, %40, %41, %42, %43, %44, %45, %46, %47, %48, %49, %50, %51, %52, %53, %54, %55, %56, %57, %58, %59, %60, %61, %62, %63}, da, db, q, 1, 1, 0, 0;\n"
    "add.s64 da, da, 2;\n"
    "add.s64 db, db, 2;\n"
    "wgmma.mma_async.sync.aligned.m64n128k16.f32.bf16.bf16 {%0, %1, %2, %3, %4, %5, %6, %7, %8, %9, %10, %11, %12, %13, %14, %15, %16, %17, %18, %19, %20, %21, %22, %23, %24, %25, %26, %27, %28, %29, %30, %31, %32, %33, %34, %35, %36, %37, %38, %39, %40, %41, %42, %43, %44, %45, %46, %47, %48, %49, %50, %51, %52, %53, %54, %55, %56, %57, %58, %59, %60, %61, %62, %63}, da, db, q, 1, 1, 0, 0;\n"
    "add.s64 da, da, 2;\n"
    "add.s64 db, db, 2;\n"
    "wgmma.mma_async.sync.aligned.m64n128k16.f32.bf16.bf16 {%0, %1, %2, %3, %4, %5, %6, %7, %8, %9, %10, %11, %12, %13, %14, %15, %16, %17, %18, %19, %20, %21, %22, %23, %24, %25, %26, %27, %28, %29, %30, %31, %32, %33, %34, %35, %36, %37, %38, %39, %40, %41, %42, %43, %44, %45, %46, %47, %48, %49, %50, %51, %52, %53, %54, %55, %56, %57, %58, %59, %60, %61, %62, %63}, da, db, q, 1, 1, 0, 0;\n"
    "add.s64 da, da, 2;\n"
    "add.s64 db, db, 2;\n"
    "wgmma.mma_async.sync.aligned.m64n128k16.f32.bf16.bf16 {%0, %1, %2, %3, %4, %5, %6, %7, %8, %9, %10, %11, %12, %13, %14, %15, %16, %17, %18, %19, %20, %21, %22, %23, %24, %25, %26, %27, %28, %29, %30, %31, %32, %33, %34, %35, %36, %37, %38, %39, %40, %41, %42, %43, %44, %45, %46, %47, %48, %49, %50, %51, %52, %53, %54, %55, %56, %57, %58, %59, %60, %61, %62, %63}, da, db, q, 1, 1, 0, 0;\n"
    "}\n"
    : "=f"(d[0]), "=f"(d[1]), "=f"(d[2]), "=f"(d[3]), "=f"(d[4]), "=f"(d[5]), "=f"(d[6]), "=f"(d[7]),
      "=f"(d[8]), "=f"(d[9]), "=f"(d[10]), "=f"(d[11]), "=f"(d[12]), "=f"(d[13]), "=f"(d[14]), "=f"(d[15]),
      "=f"(d[16]), "=f"(d[17]), "=f"(d[18]), "=f"(d[19]), "=f"(d[20]), "=f"(d[21]), "=f"(d[22]), "=f"(d[23]),
      "=f"(d[24]), "=f"(d[25]), "=f"(d[26]), "=f"(d[27]), "=f"(d[28]), "=f"(d[29]), "=f"(d[30]), "=f"(d[31]),
      "=f"(d[32]), "=f"(d[33]), "=f"(d[34]), "=f"(d[35]), "=f"(d[36]), "=f"(d[37]), "=f"(d[38]), "=f"(d[39]),
      "=f"(d[40]), "=f"(d[41]), "=f"(d[42]), "=f"(d[43]), "=f"(d[44]), "=f"(d[45]), "=f"(d[46]), "=f"(d[47]),
      "=f"(d[48]), "=f"(d[49]), "=f"(d[50]), "=f"(d[51]), "=f"(d[52]), "=f"(d[53]), "=f"(d[54]), "=f"(d[55]),
      "=f"(d[56]), "=f"(d[57]), "=f"(d[58]), "=f"(d[59]), "=f"(d[60]), "=f"(d[61]), "=f"(d[62]), "=f"(d[63])
    : "r"(da), "r"(db));
}
__device__ __forceinline__ void gemm_pv(float (&d)[64], const uint32_t (&a)[32], uint32_t db, int acc) {
  asm volatile(
    "{\n"
    ".reg .pred p, q, g;\n"
    ".reg .b64 da, db;\n"
    ".reg .b32 mt;\n"
    "setp.ne.b32 p, %97, 0;\n"
    "setp.eq.b32 q, 0, 0;\n"
    "mov.b64 db, {%96, 0x40000040};\n"
    "wgmma.mma_async.sync.aligned.m64n128k16.f32.bf16.bf16 {%0, %1, %2, %3, %4, %5, %6, %7, %8, %9, %10, %11, %12, %13, %14, %15, %16, %17, %18, %19, %20, %21, %22, %23, %24, %25, %26, %27, %28, %29, %30, %31, %32, %33, %34, %35, %36, %37, %38, %39, %40, %41, %42, %43, %44, %45, %46, %47, %48, %49, %50, %51, %52, %53, %54, %55, %56, %57, %58, %59, %60, %61, %62, %63}, {%64, %65, %66, %67}, db, p, 1, 1, 1;\n"
    "add.s64 db, db, 128;\n"
    "wgmma.mma_async.sync.aligned.m64n128k16.f32.bf16.bf16 {%0, %1, %2, %3, %4, %5, %6, %7, %8, %9, %10, %11, %12, %13, %14, %15, %16, %17, %18, %19, %20, %21, %22, %23, %24, %25, %26, %27, %28, %29, %30, %31, %32, %33, %34, %35, %36, %37, %38, %39, %40, %41, %42, %43, %44, %45, %46, %47, %48, %49, %50, %51, %52, %53, %54, %55, %56, %57, %58, %59, %60, %61, %62, %63}, {%68, %69, %70, %71}, db, q, 1, 1, 1;\n"
    "add.s64 db, db, 128;\n"
    "wgmma.mma_async.sync.aligned.m64n128k16.f32.bf16.bf16 {%0, %1, %2, %3, %4, %5, %6, %7, %8, %9, %10, %11, %12, %13, %14, %15, %16, %17, %18, %19, %20, %21, %22, %23, %24, %25, %26, %27, %28, %29, %30, %31, %32, %33, %34, %35, %36, %37, %38, %39, %40, %41, %42, %43, %44, %45, %46, %47, %48, %49, %50, %51, %52, %53, %54, %55, %56, %57, %58, %59, %60, %61, %62, %63}, {%72, %73, %74, %75}, db, q, 1, 1, 1;\n"
    "add.s64 db, db, 128;\n"
    "wgmma.mma_async.sync.aligned.m64n128k16.f32.bf16.bf16 {%0, %1, %2, %3, %4, %5, %6, %7, %8, %9, %10, %11, %12, %13, %14, %15, %16, %17, %18, %19, %20, %21, %22, %23, %24, %25, %26, %27, %28, %29, %30, %31, %32, %33, %34, %35, %36, %37, %38, %39, %40, %41, %42, %43, %44, %45, %46, %47, %48, %49, %50, %51, %52, %53, %54, %55, %56, %57, %58, %59, %60, %61, %62, %63}, {%76, %77, %78, %79}, db, q, 1, 1, 1;\n"
    "add.s64 db, db, 128;\n"
    "wgmma.mma_async.sync.aligned.m64n128k16.f32.bf16.bf16 {%0, %1, %2, %3, %4, %5, %6, %7, %8, %9, %10, %11, %12, %13, %14, %15, %16, %17, %18, %19, %20, %21, %22, %23, %24, %25, %26, %27, %28, %29, %30, %31, %32, %33, %34, %35, %36, %37, %38, %39, %40, %41, %42, %43, %44, %45, %46, %47, %48, %49, %50, %51, %52, %53, %54, %55, %56, %57, %58, %59, %60, %61, %62, %63}, {%80, %81, %82, %83}, db, q, 1, 1, 1;\n"
    "add.s64 db, db, 128;\n"
    "wgmma.mma_async.sync.aligned.m64n128k16.f32.bf16.bf16 {%0, %1, %2, %3, %4, %5, %6, %7, %8, %9, %10, %11, %12, %13, %14, %15, %16, %17, %18, %19, %20, %21, %22, %23, %24, %25, %26, %27, %28, %29, %30, %31, %32, %33, %34, %35, %36, %37, %38, %39, %40, %41, %42, %43, %44, %45, %46, %47, %48, %49, %50, %51, %52, %53, %54, %55, %56, %57, %58, %59, %60, %61, %62, %63}, {%84, %85, %86, %87}, db, q, 1, 1, 1;\n"
    "add.s64 db, db, 128;\n"
    "wgmma.mma_async.sync.aligned.m64n128k16.f32.bf16.bf16 {%0, %1, %2, %3, %4, %5, %6, %7, %8, %9, %10, %11, %12, %13, %14, %15, %16, %17, %18, %19, %20, %21, %22, %23, %24, %25, %26, %27, %28, %29, %30, %31, %32, %33, %34, %35, %36, %37, %38, %39, %40, %41, %42, %43, %44, %45, %46, %47, %48, %49, %50, %51, %52, %53, %54, %55, %56, %57, %58, %59, %60, %61, %62, %63}, {%88, %89, %90, %91}, db, q, 1, 1, 1;\n"
    "add.s64 db, db, 128;\n"
    "wgmma.mma_async.sync.aligned.m64n128k16.f32.bf16.bf16 {%0, %1, %2, %3, %4, %5, %6, %7, %8, %9, %10, %11, %12, %13, %14, %15, %16, %17, %18, %19, %20, %21, %22, %23, %24, %25, %26, %27, %28, %29, %30, %31, %32, %33, %34, %35, %36, %37, %38, %39, %40, %41, %42, %43, %44, %45, %46, %47, %48, %49, %50, %51, %52, %53, %54, %55, %56, %57, %58, %59, %60, %61, %62, %63}, {%92, %93, %94, %95}, db, q, 1, 1, 1;\n"
    "}\n"
    : "+f"(d[0]), "+f"(d[1]), "+f"(d[2]), "+f"(d[3]), "+f"(d[4]), "+f"(d[5]), "+f"(d[6]), "+f"(d[7]),
      "+f"(d[8]), "+f"(d[9]), "+f"(d[10]), "+f"(d[11]), "+f"(d[12]), "+f"(d[13]), "+f"(d[14]), "+f"(d[15]),
      "+f"(d[16]), "+f"(d[17]), "+f"(d[18]), "+f"(d[19]), "+f"(d[20]), "+f"(d[21]), "+f"(d[22]), "+f"(d[23]),
      "+f"(d[24]), "+f"(d[25]), "+f"(d[26]), "+f"(d[27]), "+f"(d[28]), "+f"(d[29]), "+f"(d[30]), "+f"(d[31]),
      "+f"(d[32]), "+f"(d[33]), "+f"(d[34]), "+f"(d[35]), "+f"(d[36]), "+f"(d[37]), "+f"(d[38]), "+f"(d[39]),
      "+f"(d[40]), "+f"(d[41]), "+f"(d[42]), "+f"(d[43]), "+f"(d[44]), "+f"(d[45]), "+f"(d[46]), "+f"(d[47]),
      "+f"(d[48]), "+f"(d[49]), "+f"(d[50]), "+f"(d[51]), "+f"(d[52]), "+f"(d[53]), "+f"(d[54]), "+f"(d[55]),
      "+f"(d[56]), "+f"(d[57]), "+f"(d[58]), "+f"(d[59]), "+f"(d[60]), "+f"(d[61]), "+f"(d[62]), "+f"(d[63])
    : "r"(a[0]), "r"(a[1]), "r"(a[2]), "r"(a[3]), "r"(a[4]), "r"(a[5]), "r"(a[6]), "r"(a[7]), "r"(a[8]), "r"(a[9]), "r"(a[10]), "r"(a[11]), "r"(a[12]), "r"(a[13]), "r"(a[14]), "r"(a[15]), "r"(a[16]), "r"(a[17]), "r"(a[18]), "r"(a[19]), "r"(a[20]), "r"(a[21]), "r"(a[22]), "r"(a[23]), "r"(a[24]), "r"(a[25]), "r"(a[26]), "r"(a[27]), "r"(a[28]), "r"(a[29]), "r"(a[30]), "r"(a[31]), "r"(db), "r"(acc));
}
__device__ __forceinline__ void gemm_proj(float (&d)[112], uint32_t da, uint32_t db) {
  asm volatile(
    "{\n"
    ".reg .pred p, q, g;\n"
    ".reg .b64 da, db;\n"
    ".reg .b32 mt;\n"
    "setp.ne.b32 p, 1, 0;\n"
    "setp.eq.b32 q, 0, 0;\n"
    "mov.b64 da, {%112, 0x40000040};\n"
    "mov.b64 db, {%113, 0x40000040};\n"
    "wgmma.mma_async.sync.aligned.m64n224k16.f32.bf16.bf16 {%0, %1, %2, %3, %4, %5, %6, %7, %8, %9, %10, %11, %12, %13, %14, %15, %16, %17, %18, %19, %20, %21, %22, %23, %24, %25, %26, %27, %28, %29, %30, %31, %32, %33, %34, %35, %36, %37, %38, %39, %40, %41, %42, %43, %44, %45, %46, %47, %48, %49, %50, %51, %52, %53, %54, %55, %56, %57, %58, %59, %60, %61, %62, %63, %64, %65, %66, %67, %68, %69, %70, %71, %72, %73, %74, %75, %76, %77, %78, %79, %80, %81, %82, %83, %84, %85, %86, %87, %88, %89, %90, %91, %92, %93, %94, %95, %96, %97, %98, %99, %100, %101, %102, %103, %104, %105, %106, %107, %108, %109, %110, %111}, da, db, p, 1, 1, 1, 0;\n"
    "add.s64 da, da, 128;\n"
    "add.s64 db, db, 2;\n"
    "wgmma.mma_async.sync.aligned.m64n224k16.f32.bf16.bf16 {%0, %1, %2, %3, %4, %5, %6, %7, %8, %9, %10, %11, %12, %13, %14, %15, %16, %17, %18, %19, %20, %21, %22, %23, %24, %25, %26, %27, %28, %29, %30, %31, %32, %33, %34, %35, %36, %37, %38, %39, %40, %41, %42, %43, %44, %45, %46, %47, %48, %49, %50, %51, %52, %53, %54, %55, %56, %57, %58, %59, %60, %61, %62, %63, %64, %65, %66, %67, %68, %69, %70, %71, %72, %73, %74, %75, %76, %77, %78, %79, %80, %81, %82, %83, %84, %85, %86, %87, %88, %89, %90, %91, %92, %93, %94, %95, %96, %97, %98, %99, %100, %101, %102, %103, %104, %105, %106, %107, %108, %109, %110, %111}, da, db, q, 1, 1, 1, 0;\n"
    "add.s64 da, da, 128;\n"
    "add.s64 db, db, 2;\n"
    "wgmma.mma_async.sync.aligned.m64n224k16.f32.bf16.bf16 {%0, %1, %2, %3, %4, %5, %6, %7, %8, %9, %10, %11, %12, %13, %14, %15, %16, %17, %18, %19, %20, %21, %22, %23, %24, %25, %26, %27, %28, %29, %30, %31, %32, %33, %34, %35, %36, %37, %38, %39, %40, %41, %42, %43, %44, %45, %46, %47, %48, %49, %50, %51, %52, %53, %54, %55, %56, %57, %58, %59, %60, %61, %62, %63, %64, %65, %66, %67, %68, %69, %70, %71, %72, %73, %74, %75, %76, %77, %78, %79, %80, %81, %82, %83, %84, %85, %86, %87, %88, %89, %90, %91, %92, %93, %94, %95, %96, %97, %98, %99, %100, %101, %102, %103, %104, %105, %106, %107, %108, %109, %110, %111}, da, db, q, 1, 1, 1, 0;\n"
    "add.s64 da, da, 128;\n"
    "add.s64 db, db, 2;\n"
    "wgmma.mma_async.sync.aligned.m64n224k16.f32.bf16.bf16 {%0, %1, %2, %3, %4, %5, %6, %7, %8, %9, %10, %11, %12, %13, %14, %15, %16, %17, %18, %19, %20, %21, %22, %23, %24, %25, %26, %27, %28, %29, %30, %31, %32, %33, %34, %35, %36, %37, %38, %39, %40, %41, %42, %43, %44, %45, %46, %47, %48, %49, %50, %51, %52, %53, %54, %55, %56, %57, %58, %59, %60, %61, %62, %63, %64, %65, %66, %67, %68, %69, %70, %71, %72, %73, %74, %75, %76, %77, %78, %79, %80, %81, %82, %83, %84, %85, %86, %87, %88, %89, %90, %91, %92, %93, %94, %95, %96, %97, %98, %99, %100, %101, %102, %103, %104, %105, %106, %107, %108, %109, %110, %111}, da, db, q, 1, 1, 1, 0;\n"
    "}\n"
    : "+f"(d[0]), "+f"(d[1]), "+f"(d[2]), "+f"(d[3]), "+f"(d[4]), "+f"(d[5]), "+f"(d[6]), "+f"(d[7]),
      "+f"(d[8]), "+f"(d[9]), "+f"(d[10]), "+f"(d[11]), "+f"(d[12]), "+f"(d[13]), "+f"(d[14]), "+f"(d[15]),
      "+f"(d[16]), "+f"(d[17]), "+f"(d[18]), "+f"(d[19]), "+f"(d[20]), "+f"(d[21]), "+f"(d[22]), "+f"(d[23]),
      "+f"(d[24]), "+f"(d[25]), "+f"(d[26]), "+f"(d[27]), "+f"(d[28]), "+f"(d[29]), "+f"(d[30]), "+f"(d[31]),
      "+f"(d[32]), "+f"(d[33]), "+f"(d[34]), "+f"(d[35]), "+f"(d[36]), "+f"(d[37]), "+f"(d[38]), "+f"(d[39]),
      "+f"(d[40]), "+f"(d[41]), "+f"(d[42]), "+f"(d[43]), "+f"(d[44]), "+f"(d[45]), "+f"(d[46]), "+f"(d[47]),
      "+f"(d[48]), "+f"(d[49]), "+f"(d[50]), "+f"(d[51]), "+f"(d[52]), "+f"(d[53]), "+f"(d[54]), "+f"(d[55]),
      "+f"(d[56]), "+f"(d[57]), "+f"(d[58]), "+f"(d[59]), "+f"(d[60]), "+f"(d[61]), "+f"(d[62]), "+f"(d[63]),
      "+f"(d[64]), "+f"(d[65]), "+f"(d[66]), "+f"(d[67]), "+f"(d[68]), "+f"(d[69]), "+f"(d[70]), "+f"(d[71]),
      "+f"(d[72]), "+f"(d[73]), "+f"(d[74]), "+f"(d[75]), "+f"(d[76]), "+f"(d[77]), "+f"(d[78]), "+f"(d[79]),
      "+f"(d[80]), "+f"(d[81]), "+f"(d[82]), "+f"(d[83]), "+f"(d[84]), "+f"(d[85]), "+f"(d[86]), "+f"(d[87]),
      "+f"(d[88]), "+f"(d[89]), "+f"(d[90]), "+f"(d[91]), "+f"(d[92]), "+f"(d[93]), "+f"(d[94]), "+f"(d[95]),
      "+f"(d[96]), "+f"(d[97]), "+f"(d[98]), "+f"(d[99]), "+f"(d[100]), "+f"(d[101]), "+f"(d[102]), "+f"(d[103]),
      "+f"(d[104]), "+f"(d[105]), "+f"(d[106]), "+f"(d[107]), "+f"(d[108]), "+f"(d[109]), "+f"(d[110]), "+f"(d[111])
    : "r"(da), "r"(db));
}


constexpr int XCHUNK = SQ * 128;
constexpr int SLOT = 32768;
constexpr int TILE = 16384;
constexpr int SM_RING = 6 * TILE;
constexpr int SM_BAR = SM_RING + 4 * SLOT;
constexpr int B_FULL = 0, B_EMPTY = 4, B_PFULL = 8, B_PEMPTY = 11, NBAR = 14;
constexpr int SM_FLAG = SM_BAR + NBAR * 8;
constexpr int SM_PUB = SM_FLAG + 8;
constexpr int SM_EPOCH = SM_FLAG + 12;
constexpr int SM_TOTAL = SM_BAR + 256;
constexpr uint32_t DESC_K = 1u << 16;
constexpr uint32_t DESC_N = (16384u >> 4) << 16;

struct Maps { CUtensorMap x, wq, k, v, o, o8, ol, wo; };

constexpr float SM_C = 0.08838834764831845f * 1.4426950408889634f;
constexpr float LAZY_LIMIT = 16777216.f;

template <bool HALF>
__device__ __forceinline__ void softmax_update_max(const float (&S)[64], float (&O)[64], float (&nr)[2], float (&l)[2], bool rescale) {
  float x0 = S[0], x1 = S[2], y0 = S[1], y1 = S[3];
#pragma unroll
  for (int j = 1; j < 16; j++) {
    x0 = fmaxf(x0, S[4 * j]); y0 = fmaxf(y0, S[4 * j + 1]);
    if (!HALF) { x1 = fmaxf(x1, S[4 * j + 2]); y1 = fmaxf(y1, S[4 * j + 3]); }
  }
  x0 = fmaxf(x0, y0); x1 = fmaxf(x1, y1);
  x0 = fmaxf(x0, __shfl_xor_sync(0xffffffffu, x0, 1));
  if (!HALF) x1 = fmaxf(x1, __shfl_xor_sync(0xffffffffu, x1, 1));
  x0 = fmaxf(x0, __shfl_xor_sync(0xffffffffu, x0, 2));
  if (!HALF) x1 = fmaxf(x1, __shfl_xor_sync(0xffffffffu, x1, 2));
  x0 *= -SM_C; x1 *= -SM_C;
  if (__builtin_expect(rescale, 0)) {
    x0 = fminf(nr[0], x0); x1 = fminf(nr[1], x1);
    const float a0 = ex2(x0 - nr[0]), a1 = ex2(x1 - nr[1]);
    l[0] *= a0; l[1] *= a1;
#pragma unroll
    for (int j = 0; j < 16; j++) {
      O[4 * j] *= a0; O[4 * j + 1] *= a0;
      if (!HALF) { O[4 * j + 2] *= a1; O[4 * j + 3] *= a1; }
    }
  }
  nr[0] = x0;
  if (!HALF) nr[1] = x1;
}
template <bool HALF> __device__ __forceinline__ void sm_exp(float (&S)[64], const float (&nr)[2], int j) {
  S[4 * j]     = ex2(fmaf(S[4 * j], SM_C, nr[0]));
  S[4 * j + 1] = ex2(fmaf(S[4 * j + 1], SM_C, nr[0]));
  if (!HALF) {
    S[4 * j + 2] = ex2(fmaf(S[4 * j + 2], SM_C, nr[1]));
    S[4 * j + 3] = ex2(fmaf(S[4 * j + 3], SM_C, nr[1]));
  }
}
constexpr int SM_SPLIT = 6;
template <bool HALF>
__device__ __forceinline__ void softmax_begin(float (&S)[64], const float (&nr)[2]) {
#pragma unroll
  for (int j = 0; j < SM_SPLIT; j++) sm_exp<HALF>(S, nr, j);
  SCHED_FENCE();
}
template <bool HALF>
__device__ __forceinline__ void softmax_finish(float (&S)[64], uint32_t (&P)[32], const float (&nr)[2], float (&l)[2]) {
#pragma unroll
  for (int j = SM_SPLIT; j < 16; j++) sm_exp<HALF>(S, nr, j);
#pragma unroll
  for (int j = 0; j < 16; j++) {
    l[0] += S[4 * j]; l[0] += S[4 * j + 1];
    if (!HALF) { l[1] += S[4 * j + 2]; l[1] += S[4 * j + 3]; }
    P[2 * j] = pack_bf16(S[4 * j], S[4 * j + 1]);
    if (!HALF) P[2 * j + 1] = pack_bf16(S[4 * j + 2], S[4 * j + 3]);
  }
}

__device__ __forceinline__ uint32_t kv_slot(int n) { return (n + 2) & 3; }
__device__ __forceinline__ void issue_kv(const Maps& tm, uint32_t sbase, int n) {
  const uint32_t slot = kv_slot(n);
  const uint32_t bar = sbase + SM_BAR + (B_FULL + slot) * 8;
  mbar_expect_tx(bar, SLOT);
  tma_load_3d_stream(sbase + SM_RING + slot * SLOT, (n & 1) ? &tm.v : &tm.k, bar, 0, blockIdx.x * (2 * SK) + (n >> 1) * 128, 0);
}
__device__ __forceinline__ uint32_t px_off(int st) { return st == 0 ? XCHUNK : st == 1 ? 4 * TILE : 0; }
__device__ __forceinline__ uint32_t pw_off(int st) { return SM_RING + (st == 2 ? 3 : st) * SLOT; }
__device__ __forceinline__ void issue_proj(const Maps& tm, uint32_t sbase, int s, int st) {
  const uint32_t bar = sbase + SM_BAR + (B_PFULL + st) * 8;
  mbar_expect_tx(bar, XCHUNK + SLOT);
  tma_load_2d(sbase + px_off(st), &tm.x, bar, s * 64, (blockIdx.x >> 4) * SQ);
  tma_load_3d(sbase + pw_off(st), &tm.wq, bar, 0, s * 64, (blockIdx.x & 15) * 4);
}
__device__ __forceinline__ uint32_t wo_off(uint32_t slot) { return (slot ^ 2) * TILE; }
__device__ __forceinline__ const uint32_t* tail_flag(int head) { return g_sync + ((blockIdx.x & ~3u) + (tid_now() & 3)) * 32 + head; }
__device__ __forceinline__ void produce_tail(const Maps& tm, const uint32_t sbase, int t, uint32_t epoch, uint32_t seen) {
  if (t < 2 || t == 8) {
    if ((int)(seen - 8 * epoch) < 0) flag_wait(tail_flag(t >> 3), 8 * epoch);
    __syncwarp();
    asm volatile("fence.proxy.async.global;" ::: "memory");
  }
  if (elect_one()) {
    const uint32_t slot = kv_slot(t), bar = sbase + SM_BAR + (B_FULL + slot) * 8;
    const int k0 = (((blockIdx.x & 12) + ((t >> 1) & 3)) * 2 + (t >> 3)) * DH + (t & 1) * 64;
    mbar_expect_tx(bar, XCHUNK + TILE);
    tma_load_3d(sbase + wo_off(slot), &tm.wo, bar, 0, k0, (blockIdx.x & 3) * 2);
    tma_load_2d(sbase + SM_RING + slot * SLOT, &tm.ol, bar, k0, (blockIdx.x >> 4) * SQ);
  }
}
__device__ __forceinline__ void arrive_bar(uint32_t sbase, int idx) { if (elect_one()) mbar_arrive(sbase + SM_BAR + idx * 8); }

__device__ __forceinline__ void store_qt(const float (&A)[112], uint32_t base, uint32_t head, uint32_t tid) {
  const uint32_t lane = tid & 31, chunk = (2 * ((tid >> 5) & 3) + ((lane >> 3) & 1)) ^ (lane & 7), hi = lane >> 4;
  const uint32_t addr = base + (lane & 7) * 128 + chunk * 16;
  const uint32_t aX = addr + head * (4 * TILE) + hi * 1024, aC = addr + (head ? SM_RING + SLOT : 2 * TILE) + hi * 1024;
  const uint32_t aD = addr + 3 * TILE + head * 1024 + hi * 2048;
#pragma unroll
  for (int j = 0; j < 14; j++) {
    const uint32_t a = j < 8 ? aX + (j >> 2) * TILE + (j & 3) * 2048 : j < 12 ? aC + (j & 3) * 2048 : aD + (j & 3) * 4096;
    stmatrix_x4_t(a, pack_bf16(A[8 * j], A[8 * j + 1]), pack_bf16(A[8 * j + 2], A[8 * j + 3]),
                  pack_bf16(A[8 * j + 4], A[8 * j + 5]), pack_bf16(A[8 * j + 6], A[8 * j + 7]));
  }
}
template <bool HALF>
__device__ __forceinline__ void epi_pack(uint32_t flag, const float (&O)[64], float (&l)[2], uint32_t (&R)[32]) {
  float a = l[0], c = HALF ? 1.f : l[1];
  a += __shfl_xor_sync(0xffffffffu, a, 1);
  if (!HALF) c += __shfl_xor_sync(0xffffffffu, c, 1);
  a += __shfl_xor_sync(0xffffffffu, a, 2);
  if (!HALF) c += __shfl_xor_sync(0xffffffffu, c, 2);
  if (!(a <= LAZY_LIMIT && c <= LAZY_LIMIT)) sts32(flag, 1);
  float r0, r1;
  asm("rcp.approx.ftz.f32 %0, %1;" : "=f"(r0) : "f"(a));
  asm("rcp.approx.ftz.f32 %0, %1;" : "=f"(r1) : "f"(c));
  l[0] = 0.f; l[1] = 0.f;
#pragma unroll
  for (int j = 0; j < 16; j++) {
    R[2 * j] = pack_bf16(O[4 * j] * r0, O[4 * j + 1] * r0);
    if (!HALF) R[2 * j + 1] = pack_bf16(O[4 * j + 2] * r1, O[4 * j + 3] * r1);
  }
}
template <bool HALF, bool REDO>
__device__ __forceinline__ void epi_store(const Maps& tm, uint32_t sbase, const uint32_t (&R)[32], int row0, int head) {
  const uint32_t tid = tid_now(), lane = tid & 31, wid = tid >> 5;
  bulk_wait_read0();
  __syncwarp();
  const uint32_t stg = sbase + (head * 4 + (wid >> 2)) * TILE + (wid & 3) * 2048, sw = lane & 7;
  if (HALF) {
    const uint32_t addr = stg + sw * 128, q = lane >> 3;
#pragma unroll
    for (int kk = 0; kk < 4; kk++)
      stmatrix_x4(addr + (kk >> 1) * 8192 + ((((kk & 1) * 4 + q) ^ sw) << 4), R[8 * kk], R[8 * kk + 2], R[8 * kk + 4], R[8 * kk + 6]);
  } else {
    const uint32_t addr = stg + (sw + 8 * ((lane >> 3) & 1)) * 128, hi = lane >> 4;
#pragma unroll
    for (int kk = 0; kk < 8; kk++)
      stmatrix_x4(addr + (kk >> 2) * 8192 + ((((kk & 3) * 2 + hi) ^ sw) << 4), R[4 * kk], R[4 * kk + 1], R[4 * kk + 2], R[4 * kk + 3]);
  }
  fence_async_smem();
  __syncwarp();
  if (elect_one() && !(REDO && head == 0 && lds32(sbase + SM_PUB))) {
    const int row = (blockIdx.x >> 4) * SQ + row0 + (wid & 3) * (HALF ? 8 : 16), col = ((blockIdx.x & 15) * 2 + head) * DH;
    tma_store_2d(HALF ? &tm.o8 : &tm.o, stg, col, row);
    tma_store_2d(HALF ? &tm.o8 : &tm.o, stg + 8192, col + 64, row);
    bulk_commit();
  }
  __syncwarp();
}
template <bool HALF, bool REDO>
__device__ __forceinline__ void epilogue_tile(const Maps& tm, uint32_t sbase, const float (&O)[64], float (&l)[2], int row0, int head) {
  uint32_t R[32];
  epi_pack<HALF>(sbase + SM_FLAG + head * 4, O, l, R);
  epi_store<HALF, REDO>(tm, sbase, R, row0, head);
}

__device__ __forceinline__ void qproj(const Maps& tm, const uint32_t sbase) {
  const uint32_t tid = tid_now(), wid = uni(tid >> 5), wg = wid >> 2;
  const uint32_t bars = sbase + SM_BAR;
  float A0[112], A1[112];
#pragma unroll
  for (int i = 0; i < 112; i++) { A0[i] = 0.f; A1[i] = 0.f; }
  int st = 0, ph = 0;
#pragma unroll 1
  for (int s = 0; s < 8; s++) {
    mbar_wait(bars + (B_PFULL + st) * 8, ph);
    const uint32_t da = DESC_K + (((sbase + pw_off(st)) >> 4) + wg * 1024), db = DESC_K + ((sbase + px_off(st)) >> 4);
    wg_fence();
    gemm_proj(A0, da, db);
    gemm_proj(A1, da + 512, db);
    wg_commit();
    wg_wait<1>();
    if (s > 0) {
      const int pst = st == 0 ? 2 : st - 1, pph = st == 0 ? ph ^ 1 : ph;
      arrive_bar(sbase, B_PEMPTY + pst);
      if (tid == 160 && s == 4) sts32(sbase + SM_EPOCH, ld_relaxed(g_sync + blockIdx.x * 32 + 4) + 1);
      if (wid == 4) {
        mbar_wait(bars + (B_PEMPTY + pst) * 8, pph);
        if (elect_one()) {
          if (s + 2 < 8) issue_proj(tm, sbase, s + 2, pst);
          else issue_kv(tm, sbase, s - 5);
        }
      }
    }
    if (++st == 3) { st = 0; ph ^= 1; }
  }
  wg_wait<0>();
  reg_fence(A0); reg_fence(A1);
  arrive_bar(sbase, B_PEMPTY + 1);
  mbar_wait(bars + (B_PEMPTY + wg) * 8, 0);
  store_qt(A0, sbase, wg, tid);
  store_qt(A1, sbase + 8192, wg, tid);
  fence_async_smem();
  if (wg == 0) { bar_sync(3, 128); bar_arrive(5, 256); } else bar_sync(5, 256);
  if (wid == 4) {
    if (elect_one()) {
      bulk_store(g_Q2 + (size_t)blockIdx.x * TILE, sbase + SM_RING + SLOT, TILE);
      bulk_commit();
    }
  }
}

template <int WG, bool exact>
__device__ __forceinline__ bool attention(const Maps& tm, const uint32_t sbase, float (&S)[64], float (&OX)[64], float (&OY)[64],
                                          uint32_t (&P)[32], float (&mX)[2], float (&lX)[2]) {
  const uint32_t tid = threadIdx.x;
  constexpr bool YH = (WG == 1);
  const uint32_t bars = sbase + SM_BAR;
  const uint32_t ring4 = (sbase + SM_RING) >> 4;
  const uint32_t warp_u = uni((tid >> 5) & 3);
  const uint32_t dqX = DESC_K + ((sbase + WG * TILE) >> 4), dqY = DESC_K + ((sbase + (2 + WG) * TILE) >> 4);
  auto pp_sync = [&]() { bar_sync(1 + WG, 256); };
  auto pp_arrive = [&]() { bar_arrive(2 - WG, 256); };
  auto acquire = [&](int n) { if (WG == 0) mbar_wait(bars + (B_FULL + kv_slot(n)) * 8, (n >> 2) & 1); };
  auto doomed = [&]() { return !exact && uni(lds32(sbase + SM_FLAG)) != 0; };
  uint32_t seen = 0;
  auto refill = [&](int m, const CUtensorMap* map) {
    refill_stream(bars + kv_slot(m) * 8, ((m >> 2) & 1) ^ 1, sbase + SM_RING + kv_slot(m) * SLOT, map, blockIdx.x * (2 * SK) + (m >> 1) * 128);
  };
  auto refill_tail = [&](int t) {
    if (doomed()) return;
    mbar_wait(bars + (B_EMPTY + kv_slot(t)) * 8, 1);
    const uint32_t epoch = lds32(sbase + SM_EPOCH);
    produce_tail(tm, sbase, t, epoch, t == 1 ? 8 * epoch : seen);
  };
  if (WG == 1 && warp_u == 0) {
    bulk_wait0();
    __syncwarp();
    if (elect_one()) issue_kv(tm, sbase, 3);
  }
  float mY[2] = {0.f, 0.f}, lY[2] = {0.f, 0.f};
#pragma unroll 1
  for (int n = 0; ; n += 2) {
    const bool first = (n & 15) == 0, last = n == 14;
    const uint32_t tg = (n & 2) << 11;
    {
      if (WG == 1 && warp_u == 0) {
        if (__builtin_expect((uint32_t)(n - 2) < 28u, 1)) refill(n + 3, &tm.v);
        else if (n == 30) refill_tail(1);
      }
      if (WG == 0 && __builtin_expect(n == 16, 0)) acquire(17);
      pp_sync();
      wg_fence();
      gemm_qk_keep(S, dqY + (WG == 1 ? (n & 16) << 2 : 0), DESC_K + ring4 + 0x1000 - tg);
      wg_commit();
      if (WG == 0) { acquire(n + 1); wg_fence(); }
      gemm_pv(OX, P, DESC_N + ring4 + 0x1800 - tg, !first);
      wg_commit();
      pp_arrive();
      if (exact) wg_wait<0>(); else wg_wait<1>();
      reg_fence(S);
      arrive_bar(sbase, B_EMPTY + kv_slot(n));
      if (__builtin_expect(first || exact, 0)) {
        if (n == 16) epilogue_tile<YH, exact>(tm, sbase, OY, lY, 128 + WG * 64, 0);
        softmax_update_max<YH>(S, OY, mY, lY, !first);
      }
      softmax_begin<YH>(S, mY);
      wg_wait<0>();
      reg_fence(OX); reg_fence(P);
      SCHED_FENCE();
      if (WG == 1 && warp_u == 1 && n < 28) refill(n + 4, &tm.k);
      softmax_finish<YH>(S, P, mY, lY);
      if (WG == 1 && warp_u == 1) {
        if (__builtin_expect((0x54005000 >> n) & 1, 0)) {
          const uint32_t bar17 = bars + (B_FULL + kv_slot(17)) * 8;
          if (n == 12) { if (elect_one()) asm volatile("mbarrier.expect_tx.shared::cta.b64 [%0], %1;" :: "r"(bar17), "r"(TILE) : "memory"); }
          else if (n == 14) { if (elect_one()) bulk_load(sbase + 2 * TILE, g_Q2 + (size_t)blockIdx.x * TILE, TILE, bar17); }
          else if (n == 26) seen = ld_relaxed(tail_flag(0));
          else refill_tail(n - 28);
        }
      }
      if (__builtin_expect((n & 22) == 22, 0)) {
        if (n == 30) break;
        bulk_wait0();
        __syncwarp();
        if (elect_one() && !lds32(sbase + (exact ? SM_PUB : SM_FLAG))) red_relaxed(g_sync + blockIdx.x * 32);
      }
    }
    {
      acquire(n + 2);
      pp_sync();
      wg_fence();
      if (YH) gemm_qk_fresh(S, dqX + (((n + 2) & 16) << 8), DESC_K + ring4 + tg);
      else gemm_qk_keep(S, dqX + (((n + 2) & 16) << 8), DESC_K + ring4 + tg);
      wg_commit();
      gemm_pv(OY, P, DESC_N + ring4 + 0x800 + (tg ^ 0x1000), !first);
      wg_commit();
      pp_arrive();
      if (exact) wg_wait<0>(); else wg_wait<1>();
      reg_fence(S);
      if (__builtin_expect(last || exact, 0)) {
        if (last) epilogue_tile<false, exact>(tm, sbase, OX, lX, WG * 64, 0);
        softmax_update_max<false>(S, OX, mX, lX, !last);
      }
      softmax_begin<false>(S, mX);
      wg_wait<0>();
      reg_fence(OY); reg_fence(P);
      SCHED_FENCE();
      arrive_bar(sbase, B_EMPTY + kv_slot(n + 1));
      softmax_finish<false>(S, P, mX, lX);
    }
  }
  pp_sync();
  wg_fence();
  gemm_pv(OY, P, DESC_N + ring4 + kv_slot(31) * (SLOT >> 4), 1);
  wg_commit();
  if (WG == 0) pp_arrive();
  SCHED_FENCE();
  epilogue_tile<false, exact>(tm, sbase, OX, lX, WG * 64, 1);
  wg_wait<0>();
  reg_fence(OY); reg_fence(P);
  epi_pack<YH>(sbase + SM_FLAG + 4, OY, lY, P);
  __syncwarp();
  arrive_bar(sbase, B_EMPTY + kv_slot(31));
  return !doomed();
}

template <bool exact>
__device__ __forceinline__ bool tail(const Maps& tm, const uint32_t sbase, const uint32_t (&P)[32], uint8_t* out) {
  const uint32_t tid = tid_now(), lane = tid & 31, wid = uni(tid >> 5), wg = wid >> 2;
  const uint32_t bars = sbase + SM_BAR;
  const uint32_t epoch = lds32(sbase + SM_EPOCH);
  uint32_t seen = 0;
  float acc[112];
#pragma unroll
  for (int i = 0; i < 112; i++) acc[i] = 0.f;
#pragma unroll 1
  for (int t = 0; t < 16; t++) {
    const uint32_t slot = kv_slot(t);
    mbar_wait(bars + (B_FULL + slot) * 8, (t >> 2) & 1);
    if (t == 13 && wg == 1) bar_sync(4, 256);
    const uint32_t da = DESC_K + ((sbase + wo_off(slot) + wg * 8192) >> 4), db = DESC_K + ((sbase + SM_RING + slot * SLOT) >> 4);
    wg_fence();
    gemm_proj(acc, da, db);
    wg_commit();
    if (t == 15 && wg == 0) bar_arrive(4, 256);
    if (t == 1) {
      if (wg == 0) epi_store<false, false>(tm, sbase, P, 128, 1); else epi_store<true, false>(tm, sbase, P, 192, 1);
    }
    if (t == 3) {
      bar_sync(5, 256);
      if (!exact) {
        if (__builtin_expect(uni(lds32(sbase + SM_FLAG + 4)) != 0, 0)) {
          wg_wait<0>();
          for (int i = 4; i < 6; i++) mbar_wait(bars + (B_FULL + kv_slot(i)) * 8, 1);
          sts32(sbase + SM_PUB, 1);
          return false;
        }
      }
      bulk_wait0();
      __syncwarp();
      if (elect_one()) red_relaxed(g_sync + blockIdx.x * 32 + 1);
    }
    if (t > 0) {
      wg_wait<1>();
      arrive_bar(sbase, B_EMPTY + kv_slot(t - 1));
    }
    if (wid == 4 && t < 13) {
      mbar_wait(bars + (B_EMPTY + kv_slot(t + 3)) * 8, (((t + 3) >> 2) & 1) ^ 1);
      produce_tail(tm, sbase, t + 3, epoch, seen);
      if (t == 4) seen = ld_relaxed(tail_flag(1));
    }
  }
  wg_wait<0>();
  reg_fence(acc);
  const uint32_t kg = (blockIdx.x >> 2) & 3, tag = epoch << 16;
#pragma unroll
  for (int q = 0; q < 4; q++) {
    uint4* p = g_part + (((blockIdx.x & ~12u) + q * 4) * 3 + (kg < q ? kg : kg - 1)) * (4 * 256) + tid;
#pragma unroll
    for (int i = 0; i < 4; i++) {
      const float* a = &acc[28 * q + 7 * i];
      const uint32_t w0 = pack_bf16(a[0], a[1]), w1 = pack_bf16(a[2], a[3]), w2 = pack_bf16(a[4], a[5]), w3 = pack_bf16(a[6], 0.f) | tag;
      if (q != kg) st_b128(p + i * 256, w0, w1, w2, w3);
    }
  }
  __syncwarp();
  if (lane < 4 && lane != kg) red_relaxed(g_sync + ((blockIdx.x & ~12u) + lane * 4) * 32 + 2 + wg);
  float r[28];
#pragma unroll
  for (int i = 0; i < 28; i++) r[i] = (kg & 2) ? ((kg & 1) ? acc[84 + i] : acc[56 + i]) : ((kg & 1) ? acc[28 + i] : acc[i]);
  {
    const uint4* p = g_part + blockIdx.x * 3 * (4 * 256) + tid;
    uint4 v[12];
    if (lane == 0) {
      const uint32_t* q = g_sync + blockIdx.x * 32 + 2 + wg;
      for (uint32_t n = 0; (int)(ld_relaxed(q) - 12 * epoch) < 0; n++) { __nanosleep(50); if (n > 20000000u) __trap(); }
    }
    __syncwarp();
    for (uint32_t n = 0; ; n++) {
      uint32_t bad = 0;
#pragma unroll
      for (int i = 0; i < 12; i++) v[i] = ld_b128(p + i * 256);
#pragma unroll
      for (int i = 0; i < 12; i++) bad |= v[i].w ^ tag;
      if (bad < 0x10000u) break;
      __nanosleep(50);
      if (n > 4000000u) __trap();
    }
#pragma unroll
    for (int i = 0; i < 4; i++) {
      r[7 * i]     += (bf_lo(v[i].x) + bf_lo(v[i + 4].x)) + bf_lo(v[i + 8].x);
      r[7 * i + 1] += (bf_hi(v[i].x) + bf_hi(v[i + 4].x)) + bf_hi(v[i + 8].x);
      r[7 * i + 2] += (bf_lo(v[i].y) + bf_lo(v[i + 4].y)) + bf_lo(v[i + 8].y);
      r[7 * i + 3] += (bf_hi(v[i].y) + bf_hi(v[i + 4].y)) + bf_hi(v[i + 8].y);
      r[7 * i + 4] += (bf_lo(v[i].z) + bf_lo(v[i + 4].z)) + bf_lo(v[i + 8].z);
      r[7 * i + 5] += (bf_hi(v[i].z) + bf_hi(v[i + 4].z)) + bf_hi(v[i + 8].z);
      r[7 * i + 6] += (bf_lo(v[i].w) + bf_lo(v[i + 4].w)) + bf_lo(v[i + 8].w);
    }
  }
  __syncwarp();
  const uint32_t stg = sbase + (4 + wg) * TILE + (wid & 3) * 2048;
  const uint32_t addr = stg + ((lane & 7) + ((lane >> 4) << 3)) * 32 + ((lane >> 3) & 1) * 16;
#pragma unroll
  for (int j = 0; j < 3; j++)
    stmatrix_x4_t(addr + j * 512, pack_bf16(r[8 * j], r[8 * j + 1]), pack_bf16(r[8 * j + 2], r[8 * j + 3]),
                  pack_bf16(r[8 * j + 4], r[8 * j + 5]), pack_bf16(r[8 * j + 6], r[8 * j + 7]));
  stmatrix_x2_t(addr + 3 * 512, pack_bf16(r[24], r[25]), pack_bf16(r[26], r[27]));
  __syncwarp();
  uint8_t* o = out + ((size_t)((blockIdx.x >> 4) * SQ + kg * 56 + (lane >> 1)) * DM + (blockIdx.x & 3) * 128 + wid * 16 + (lane & 1) * 8) * 2;
#pragma unroll
  for (int j = 0; j < 4; j++) {
    if (j < 3 || lane < 16) {
      uint4 w;
      asm volatile("ld.shared.v4.u32 {%0, %1, %2, %3}, [%4];" : "=r"(w.x), "=r"(w.y), "=r"(w.z), "=r"(w.w) : "r"(stg + j * 512 + lane * 16) : "memory");
      *reinterpret_cast<uint4*>(o + j * 16 * DM * 2) = w;
    }
  }
  if (tid == 0) g_sync[blockIdx.x * 32 + 4] = epoch;
  return true;
}

template <bool exact>
__device__ __forceinline__ bool run_pass(const Maps& tm, const uint32_t sbase, uint8_t* out) {
  qproj(tm, sbase);
  SCHED_FENCE();
  uint32_t P[32];
  float S[64], OX[64], OY[64], mX[2], lX[2] = {0.f, 0.f};
  const uint32_t wg = uni(threadIdx.x >> 7);
  if (wg == 1) bar_arrive(1, 256);
  {
    mbar_wait(sbase + SM_BAR + (B_FULL + kv_slot(0)) * 8, 0);
    wg_fence();
    gemm_qk_fresh(S, DESC_K + ((sbase + wg * TILE) >> 4), DESC_K + ((sbase + SM_RING + kv_slot(0) * SLOT) >> 4));
    wg_commit();
#pragma unroll
    for (int i = 0; i < 64; i++) { OX[i] = 0.f; OY[i] = 0.f; }
    reg_fence(OX); reg_fence(OY);
    SCHED_FENCE();
    wg_wait<0>();
    reg_fence(S);
    softmax_update_max<false>(S, OX, mX, lX, false);
    softmax_begin<false>(S, mX);
    softmax_finish<false>(S, P, mX, lX);
  }
  bool ok;
  if (wg == 0) ok = attention<0, exact>(tm, sbase, S, OX, OY, P, mX, lX);
  else ok = attention<1, exact>(tm, sbase, S, OX, OY, P, mX, lX);
  SCHED_FENCE();
  return ok && tail<exact>(tm, sbase, P, out);
}

__device__ __forceinline__ void setup(const Maps& tm, const uint32_t sbase, bool again) {
  const uint32_t tid = threadIdx.x, wid = tid >> 5;
  auto init = [&](int i, int cnt) {
    if (again) asm volatile("mbarrier.inval.shared::cta.b64 [%0];" :: "r"(sbase + SM_BAR + i * 8) : "memory");
    mbar_init(sbase + SM_BAR + i * 8, cnt);
  };
  if ((tid & 31) == 0) {
    if (wid == 0) {
      for (int i = 0; i < 3; i++) init(B_PFULL + i, 1);
      init(B_FULL + 2, 1);
      asm volatile("fence.mbarrier_init.release.cluster;" ::: "memory");
      for (int i = 0; i < 3; i++) issue_proj(tm, sbase, i, i);
      issue_kv(tm, sbase, 0);
    } else if (wid >= 4) {
      init(B_EMPTY + wid - 4, 8);
      if (wid != 6) init(B_FULL + wid - 4, 1);
      if (wid < 7) init(B_PEMPTY + wid - 4, 8);
      else if (!again) { sts32(sbase + SM_FLAG, 0); sts32(sbase + SM_FLAG + 4, 0); sts32(sbase + SM_PUB, 0); }
      asm volatile("fence.mbarrier_init.release.cluster;" ::: "memory");
    }
  }
  __syncthreads();
}

__global__ void __launch_bounds__(256, 1) attn_kernel(const __grid_constant__ Maps tm, uint8_t* __restrict__ out,
                                                      const uint8_t* __restrict__ kc, const uint8_t* __restrict__ vc) {
  extern __shared__ __align__(1024) uint8_t smem[];
  const uint32_t sbase = smem_u32(smem);
  const uint32_t tid = threadIdx.x;
  if (blockIdx.x >= 128) {
    if (tid == 0) {
#pragma unroll 1
      for (int i = blockIdx.x - 128; i < 256; i += 4) {
        const int c = i & 127, n = 5 + (i >> 7) * 13 + (c % 13);
        l2_prefetch(((n & 1) ? vc : kc) + ((size_t)c * (2 * SK) + (n >> 1) * 128) * (DH * 2), SLOT);
      }
    }
    return;
  }
  setup(tm, sbase, false);
  if (__builtin_expect(!run_pass<false>(tm, sbase, out), 0)) {
    bulk_wait0();
    __syncthreads();
    setup(tm, sbase, true);
    run_pass<true>(tm, sbase, out);
  }
}

typedef CUresult (*EncFn)(CUtensorMap*, CUtensorMapDataType, cuuint32_t, void*, const cuuint64_t*, const cuuint64_t*,
                          const cuuint32_t*, const cuuint32_t*, CUtensorMapInterleave, CUtensorMapSwizzle,
                          CUtensorMapL2promotion, CUtensorMapFloatOOBfill);

void make_map(EncFn enc, CUtensorMap* tm, const void* ptr, int rank, const cuuint64_t* dims, const cuuint64_t* strides,
              const cuuint32_t* box, CUtensorMapL2promotion promo = CU_TENSOR_MAP_L2_PROMOTION_L2_256B) {
  cuuint32_t es[3] = {1, 1, 1};
  enc(tm, CU_TENSOR_MAP_DATA_TYPE_BFLOAT16, rank, const_cast<void*>(ptr), dims, strides, box, es, CU_TENSOR_MAP_INTERLEAVE_NONE,
      CU_TENSOR_MAP_SWIZZLE_128B, promo, CU_TENSOR_MAP_FLOAT_OOB_FILL_NONE);
}

}

extern "C" void kernel_launch(void* const* d_in, const int* in_sizes, int n_in, void* d_out, int out_size) {
  const void* x = d_in[0]; const void* kc = d_in[1]; const void* vc = d_in[2]; const void* wq = d_in[3]; const void* wo = d_in[4];
  static EncFn enc = nullptr;
  static void* gO = nullptr;
  if (!enc) {
    void* fn = nullptr; cudaDriverEntryPointQueryResult qr;
    cudaGetDriverEntryPoint("cuTensorMapEncodeTiled", &fn, cudaEnableDefault, &qr);
    enc = (EncFn)fn;
    cudaGetSymbolAddress(&gO, g_O);
    cudaFuncSetAttribute(attn_kernel, cudaFuncAttributeMaxDynamicSharedMemorySize, SM_TOTAL);
  }
  Maps tm;
  { cuuint64_t d[2] = {DM, ROWS}, s[1] = {DM * 2}; cuuint32_t bx[2] = {64, SQ}; make_map(enc, &tm.x, x, 2, d, s, bx); }
  { cuuint64_t d[3] = {64, DM, HD / 64}, s[2] = {HD * 2, 128}; cuuint32_t bx[3] = {64, 64, 4}; make_map(enc, &tm.wq, wq, 3, d, s, bx); }
  { cuuint64_t d[3] = {64, (cuuint64_t)NB * NH * SK, 2}, s[2] = {DH * 2, 128}; cuuint32_t bx[3] = {64, 128, 2};
    make_map(enc, &tm.k, kc, 3, d, s, bx, CU_TENSOR_MAP_L2_PROMOTION_NONE);
    make_map(enc, &tm.v, vc, 3, d, s, bx, CU_TENSOR_MAP_L2_PROMOTION_NONE); }
  { cuuint64_t d[2] = {HD, ROWS}, s[1] = {HD * 2};
    cuuint32_t b16[2] = {64, 16}, b8[2] = {64, 8}, bl[2] = {64, SQ};
    make_map(enc, &tm.o, gO, 2, d, s, b16); make_map(enc, &tm.o8, gO, 2, d, s, b8); make_map(enc, &tm.ol, gO, 2, d, s, bl); }
  { cuuint64_t d[3] = {64, HD, DM / 64}, s[2] = {DM * 2, 128}; cuuint32_t bx[3] = {64, 64, 2}; make_map(enc, &tm.wo, wo, 3, d, s, bx); }
  attn_kernel<<<132, 256, SM_TOTAL, cudaStreamPerThread>>>(tm, (uint8_t*)d_out, (const uint8_t*)kc, (const uint8_t*)vc);
}
```
